```python
import torch

def _softmax(x, axis=-1):
    return torch.softmax(x, dim=axis)
def _gelu(x):
    return torch.nn.functional.gelu(x, approximate="tanh")
def _silu(x):
    return torch.nn.functional.silu(x)
def _sigmoid(x):
    return torch.sigmoid(x)
def _layernorm(x, axis=-1, eps=1e-5):
    m = x.mean(dim=axis, keepdim=True)
    v = x.var(dim=axis, keepdim=True, unbiased=False)
    return (x - m) / torch.sqrt(v + eps)
def _scatter_add(tgt, idx, src, axis=0):
    return tgt.clone().index_add_(axis, idx, src)
def _segment_sum(src, seg, n):
    out = torch.zeros((n,) + src.shape[1:], dtype=src.dtype)
    return out.index_add_(0, seg, src)
def _pad(x, pw):
    flat = tuple(v for pair in reversed(pw) for v in pair)
    return torch.nn.functional.pad(x, flat)

kernel_name = 'standalone__deepnorm__sampling'

def setup_inputs():

    _w = (lambda a: (lambda t: t.to(torch.bfloat16) if t.is_floating_point() else t)(torch.as_tensor(a)))
    B, S, D = 1024, 8, 576
    return {
        "x": _w((lambda *s: torch.randn(*s, dtype=torch.bfloat16) * 0.05)(B, S, D)),
        "f": _w((lambda *s: torch.randn(*s, dtype=torch.bfloat16) * 0.05)(B, S, D)),
        "g": _w((lambda *s: torch.randn(*s, dtype=torch.bfloat16) * 0.05)(D) + 1.0),
        "b": _w((lambda *s: torch.randn(*s, dtype=torch.bfloat16) * 0.2)(D)),
        "alpha": _w(float(2.0)),
    }

def reference(x, f, g, b, alpha):
    return _layernorm(alpha * x + f, axis=-1) * g + b
```

```cpp
#include <cuda_runtime.h>
#include <cuda_bf16.h>
#include <stdint.h>

constexpr int D = 576;
constexpr int CH = 9;

__device__ __forceinline__ uint4 ldg_stream(const void* p) {
    uint4 v;
    asm volatile("ld.global.nc.L1::no_allocate.v4.u32 {%0,%1,%2,%3}, [%4];"
                 : "=r"(v.x), "=r"(v.y), "=r"(v.z), "=r"(v.w) : "l"(p));
    return v;
}
__device__ __forceinline__ float bf_lo(uint32_t u) { return __uint_as_float(u << 16); }
__device__ __forceinline__ float bf_hi(uint32_t u) { return __uint_as_float(u & 0xffff0000u); }
__device__ __forceinline__ uint32_t pack_bf2(float lo, float hi) {
    uint32_t r;
    asm("cvt.rn.bf16x2.f32 %0, %1, %2;" : "=r"(r) : "f"(hi), "f"(lo));
    return r;
}
__device__ __forceinline__ uint32_t hfma2_bf(uint32_t a, uint32_t b, uint32_t c) {
    uint32_t r;
    asm("fma.rn.bf16x2 %0, %1, %2, %3;" : "=r"(r) : "r"(a), "r"(b), "r"(c));
    return r;
}

__global__ void __launch_bounds__(128)
deepnorm_kernel(const uint4* __restrict__ x, const uint4* __restrict__ f,
                const uint4* __restrict__ g, const uint4* __restrict__ b,
                const unsigned short* __restrict__ alpha_p, uint4* __restrict__ out, int rows) {
    const int tid = blockIdx.x * blockDim.x + threadIdx.x;
    const int row = tid >> 3;
    const int sub = tid & 7;
    if (row >= rows) return;
    const size_t base = (size_t)row * (D / 8) + sub;
    uint4 xv[CH], fv[CH];
#pragma unroll
    for (int i = 0; i < CH; i++) { xv[i] = ldg_stream(x + base + i * 8); fv[i] = ldg_stream(f + base + i * 8); }
    const float alpha = __uint_as_float((uint32_t)alpha_p[0] << 16);
    float y[CH * 8];
    float s = 0.f;
#pragma unroll
    for (int i = 0; i < CH; i++) {
        const uint32_t xs[4] = {xv[i].x, xv[i].y, xv[i].z, xv[i].w};
        const uint32_t fs[4] = {fv[i].x, fv[i].y, fv[i].z, fv[i].w};
#pragma unroll
        for (int j = 0; j < 4; j++) {
            y[i * 8 + 2 * j]     = fmaf(alpha, bf_lo(xs[j]), bf_lo(fs[j]));
            y[i * 8 + 2 * j + 1] = fmaf(alpha, bf_hi(xs[j]), bf_hi(fs[j]));
            s += y[i * 8 + 2 * j] + y[i * 8 + 2 * j + 1];
        }
    }
    s += __shfl_xor_sync(0xffffffffu, s, 1);
    s += __shfl_xor_sync(0xffffffffu, s, 2);
    s += __shfl_xor_sync(0xffffffffu, s, 4);
    const float mean = s * (1.0f / D);
    float q = 0.f;
#pragma unroll
    for (int i = 0; i < CH * 8; i++) { y[i] -= mean; q = fmaf(y[i], y[i], q); }
    q += __shfl_xor_sync(0xffffffffu, q, 1);
    q += __shfl_xor_sync(0xffffffffu, q, 2);
    q += __shfl_xor_sync(0xffffffffu, q, 4);
    const float rstd = rsqrtf(q * (1.0f / D) + 1e-5f);
#pragma unroll
    for (int i = 0; i < CH; i++) {
        const uint4 gv = g[sub + i * 8];
        const uint4 bv = b[sub + i * 8];
        uint4 o;
        o.x = hfma2_bf(pack_bf2(y[i * 8 + 0] * rstd, y[i * 8 + 1] * rstd), gv.x, bv.x);
        o.y = hfma2_bf(pack_bf2(y[i * 8 + 2] * rstd, y[i * 8 + 3] * rstd), gv.y, bv.y);
        o.z = hfma2_bf(pack_bf2(y[i * 8 + 4] * rstd, y[i * 8 + 5] * rstd), gv.z, bv.z);
        o.w = hfma2_bf(pack_bf2(y[i * 8 + 6] * rstd, y[i * 8 + 7] * rstd), gv.w, bv.w);
        out[base + i * 8] = o;
    }
}

extern "C" void kernel_launch(void* const* d_in, const int* in_sizes, int n_in,
                              void* d_out, int out_size) {
    const uint4* x = (const uint4*)d_in[0];
    const uint4* f = (const uint4*)d_in[1];
    const uint4* g = (const uint4*)d_in[2];
    const uint4* b = (const uint4*)d_in[3];
    const unsigned short* alpha = (const unsigned short*)d_in[4];
    int rows = in_sizes[0] / D;
    int threads = 128;
    int blocks = (rows * 8 + threads - 1) / threads;
    deepnorm_kernel<<<blocks, threads>>>(x, f, g, b, alpha, (uint4*)d_out, rows);
}
```

```cpp
#include <cuda_runtime.h>
#include <cuda_bf16.h>
#include <stdint.h>

#define DN_NW 16
#define DN_GRID 103

namespace {

constexpr int kD = 576;
constexpr uint32_t kRowBytes = kD * 2;

__device__ __forceinline__ float bf_lo(uint32_t u) { return __uint_as_float(u << 16); }
__device__ __forceinline__ float bf_hi(uint32_t u) { return __uint_as_float(u & 0xffff0000u); }
__device__ __forceinline__ uint32_t pack_bf2(float lo, float hi) {
    uint32_t r;
    asm("cvt.rn.bf16x2.f32 %0, %1, %2;" : "=r"(r) : "f"(hi), "f"(lo));
    return r;
}
__device__ __forceinline__ uint32_t fma_bf2(uint32_t a, uint32_t b, uint32_t c) {
    uint32_t r;
    asm("fma.rn.bf16x2 %0, %1, %2, %3;" : "=r"(r) : "r"(a), "r"(b), "r"(c));
    return r;
}
__device__ __forceinline__ void ldg4(uint32_t* r, const void* p) {
    asm volatile("ld.global.nc.v4.u32 {%0,%1,%2,%3}, [%4];"
                 : "=r"(r[0]), "=r"(r[1]), "=r"(r[2]), "=r"(r[3]) : "l"(p));
}
__device__ __forceinline__ void ldg1(uint32_t* r, const void* p) {
    asm volatile("ld.global.nc.u32 %0, [%1];" : "=r"(r[0]) : "l"(p));
}
__device__ __forceinline__ void stg4(void* p, const uint32_t* r) {
    asm volatile("st.global.cs.v4.u32 [%4], {%0,%1,%2,%3};"
                 :: "r"(r[0]), "r"(r[1]), "r"(r[2]), "r"(r[3]), "l"(p) : "memory");
}
__device__ __forceinline__ void stg1(void* p, uint32_t v) {
    asm volatile("st.global.cs.u32 [%1], %0;" :: "r"(v), "l"(p) : "memory");
}
__device__ __forceinline__ void lds4(uint32_t* r, uint32_t a) {
    asm volatile("ld.shared.v4.u32 {%0,%1,%2,%3}, [%4];"
                 : "=r"(r[0]), "=r"(r[1]), "=r"(r[2]), "=r"(r[3]) : "r"(a));
}
__device__ __forceinline__ void lds1(uint32_t* r, uint32_t a) {
    asm volatile("ld.shared.u32 %0, [%1];" : "=r"(r[0]) : "r"(a));
}

template <int NW, int GRID, int ROWS>
__global__ void __launch_bounds__(NW * 32, 1)
deepnorm_kernel(const char* __restrict__ x, const char* __restrict__ f, const char* __restrict__ g,
                const char* __restrict__ b, const unsigned short* __restrict__ alpha_p,
                char* __restrict__ out, uint32_t rows) {
    constexpr uint32_t kStride = NW * GRID * kRowBytes;
    __shared__ __align__(128) uint32_t s_gb[2 * (kRowBytes / 4)];

    const uint32_t tid = threadIdx.x;
    const uint32_t lane = tid & 31;
    const uint32_t total = (ROWS > 0 ? (uint32_t)ROWS : rows) * kRowBytes;

    uint32_t t0 = 0, t1 = 0, t2 = 0, t3 = 0;
    {
        const uint64_t base = tid < 72 ? (uint64_t)g : (uint64_t)b - kRowBytes;
        asm volatile("{ .reg .pred q; setp.lt.u32 q, %5, 144; @q ld.global.nc.v4.u32 {%0,%1,%2,%3}, [%4]; }"
                     : "+r"(t0), "+r"(t1), "+r"(t2), "+r"(t3) : "l"(base + tid * 16), "r"(tid));
    }
    uint32_t araw;
    asm volatile("ld.global.nc.u16 %0, [%1];" : "=r"(araw) : "l"(alpha_p));

    uint32_t off = (blockIdx.x * NW + (tid >> 5)) * kRowBytes + lane * 16;
    const int tail = 1024 - (int)lane * 12;
    const bool active = ROWS > 0 ? true : off < total;
    uint32_t gv[9], bv[9], xv[9], fv[9];
    if (active) {
        ldg4(&xv[0], x + off); ldg4(&xv[4], x + off + 512); ldg1(&xv[8], x + (off + tail));
        ldg4(&fv[0], f + off); ldg4(&fv[4], f + off + 512); ldg1(&fv[8], f + (off + tail));
    }
    const uint32_t sb = (uint32_t)__cvta_generic_to_shared(s_gb);
    asm volatile("{ .reg .pred q; setp.lt.u32 q, %5, 144; @q st.shared.v4.u32 [%4], {%0,%1,%2,%3}; }"
                 :: "r"(t0), "r"(t1), "r"(t2), "r"(t3), "r"(sb + tid * 16), "r"(tid) : "memory");
    __syncthreads();
    if (!active) return;
    lds4(&gv[0], sb + lane * 16); lds4(&gv[4], sb + 512 + lane * 16); lds1(&gv[8], sb + 1024 + lane * 4);
    lds4(&bv[0], sb + kRowBytes + lane * 16); lds4(&bv[4], sb + kRowBytes + 512 + lane * 16);
    lds1(&bv[8], sb + kRowBytes + 1024 + lane * 4);
    const uint32_t a2 = araw * 0x10001u;

#pragma unroll 1
    while (true) {
        float v[18];
#pragma unroll
        for (int i = 0; i < 9; i++) {
            const uint32_t y = fma_bf2(a2, xv[i], fv[i]);
            v[2 * i] = bf_lo(y);
            v[2 * i + 1] = bf_hi(y);
        }
        const uint32_t noff = off + kStride;
        const bool more = noff < total;
        if (more) {
            ldg4(&xv[0], x + noff); ldg4(&xv[4], x + noff + 512); ldg1(&xv[8], x + (noff + tail));
            ldg4(&fv[0], f + noff); ldg4(&fv[4], f + noff + 512); ldg1(&fv[8], f + (noff + tail));
        }
        float s0 = v[0], s1 = v[1], s2 = v[2];
#pragma unroll
        for (int i = 3; i < 18; i += 3) { s0 += v[i]; s1 += v[i + 1]; s2 += v[i + 2]; }
        float m = ((s0 + s1) + s2) * (1.0f / 18.0f);
        float q0 = 0.f, q1 = 0.f, q2 = 0.f;
#pragma unroll
        for (int i = 0; i < 18; i += 3) {
            const float d0 = v[i] - m, d1 = v[i + 1] - m, d2 = v[i + 2] - m;
            q0 = fmaf(d0, d0, q0); q1 = fmaf(d1, d1, q1); q2 = fmaf(d2, d2, q2);
        }
        float q = (q0 + q1) + q2;
        float half_n = 9.0f;
#pragma unroll
        for (int o = 1; o < 32; o <<= 1) {
            const float mo = __shfl_xor_sync(0xffffffffu, m, o);
            const float qo = __shfl_xor_sync(0xffffffffu, q, o);
            const float d = mo - m;
            q = fmaf(d * half_n, d, q + qo);
            m = 0.5f * (m + mo);
            half_n *= 2.0f;
        }
        float rstd;
        asm("rsqrt.approx.ftz.f32 %0, %1;" : "=f"(rstd) : "f"(fmaf(q, 1.0f / kD, 1e-5f)));
        const float nm = -m * rstd;
        uint32_t o[9];
#pragma unroll
        for (int i = 0; i < 9; i++)
            o[i] = fma_bf2(pack_bf2(fmaf(v[2 * i], rstd, nm), fmaf(v[2 * i + 1], rstd, nm)), gv[i], bv[i]);
        stg4(out + off, &o[0]); stg4(out + off + 512, &o[4]); stg1(out + (off + tail), o[8]);
        if (!more) break;
        off = noff;
    }
}

}

extern "C" void kernel_launch(void* const* d_in, const int* in_sizes, int n_in,
                              void* d_out, int out_size) {
    (void)n_in; (void)out_size;
    const char* x = (const char*)d_in[0];
    const char* f = (const char*)d_in[1];
    const char* g = (const char*)d_in[2];
    const char* b = (const char*)d_in[3];
    const unsigned short* alpha = (const unsigned short*)d_in[4];
    const uint32_t rows = (uint32_t)(in_sizes[0] / kD);
    if (rows == 8192)
        deepnorm_kernel<DN_NW, DN_GRID, 8192><<<DN_GRID, DN_NW * 32>>>(x, f, g, b, alpha, (char*)d_out, rows);
    else
        deepnorm_kernel<16, 128, 0><<<128, 512>>>(x, f, g, b, alpha, (char*)d_out, rows);
}
```

```cpp
#include <cuda_runtime.h>
#include <cuda_bf16.h>
#include <stdint.h>

#define DN_W0 3
#define DN_D0 170
#define DN_D1 180
#define DN_TREL 11900
#define DN_HW 4
#define DN_GUARD 1

namespace {

constexpr int kD = 576;
constexpr uint32_t kRowBytes = kD * 2;
constexpr int kWarps = 16;
constexpr int kGrid = 128;
constexpr uint32_t kStride = kWarps * kGrid * kRowBytes;

__device__ __forceinline__ float bf_lo(uint32_t u) { return __uint_as_float(u << 16); }
__device__ __forceinline__ float bf_hi(uint32_t u) { return __uint_as_float(u & 0xffff0000u); }
__device__ __forceinline__ uint32_t pack_bf2(float lo, float hi) {
    uint32_t r;
    asm("cvt.rn.bf16x2.f32 %0, %1, %2;" : "=r"(r) : "f"(hi), "f"(lo));
    return r;
}
__device__ __forceinline__ uint32_t fma_bf2(uint32_t a, uint32_t b, uint32_t c) {
    uint32_t r;
    asm("fma.rn.bf16x2 %0, %1, %2, %3;" : "=r"(r) : "r"(a), "r"(b), "r"(c));
    return r;
}
__device__ __forceinline__ uint32_t now_clk() { return (uint32_t)clock(); }
__device__ __forceinline__ uint32_t now_ns() {
    uint32_t t;
    asm volatile("mov.u32 %0, %globaltimer_lo;" : "=r"(t));
    return t;
}

__device__ __forceinline__ void load_param_row(uint32_t (&r)[9], const char* p, const char* q) {
    asm volatile("ld.global.nc.v4.u32 {%0,%1,%2,%3}, [%4];" : "=r"(r[0]), "=r"(r[1]), "=r"(r[2]), "=r"(r[3]) : "l"(p));
    asm volatile("ld.global.nc.v4.u32 {%0,%1,%2,%3}, [%4+512];" : "=r"(r[4]), "=r"(r[5]), "=r"(r[6]), "=r"(r[7]) : "l"(p));
    asm volatile("ld.global.nc.u32 %0, [%1];" : "=r"(r[8]) : "l"(q));
}
__device__ __forceinline__ void load_row(uint32_t (&r)[9], const char* p, const char* q) {
    asm volatile("ld.global.nc.L1::no_allocate.v4.u32 {%0,%1,%2,%3}, [%4];"
                 : "=r"(r[0]), "=r"(r[1]), "=r"(r[2]), "=r"(r[3]) : "l"(p));
    asm volatile("ld.global.nc.L1::no_allocate.v4.u32 {%0,%1,%2,%3}, [%4+512];"
                 : "=r"(r[4]), "=r"(r[5]), "=r"(r[6]), "=r"(r[7]) : "l"(p));
    asm volatile("ld.global.nc.L1::no_allocate.u32 %0, [%1];" : "=r"(r[8]) : "l"(q));
}
__device__ __forceinline__ void store_row(char* p, char* q, const uint32_t (&r)[9]) {
    asm volatile("st.global.L1::no_allocate.v4.u32 [%4], {%0,%1,%2,%3};" :: "r"(r[0]), "r"(r[1]), "r"(r[2]), "r"(r[3]), "l"(p) : "memory");
    asm volatile("st.global.L1::no_allocate.v4.u32 [%4+512], {%0,%1,%2,%3};" :: "r"(r[4]), "r"(r[5]), "r"(r[6]), "r"(r[7]), "l"(p) : "memory");
    asm volatile("st.global.L1::no_allocate.u32 [%1], %0;" :: "r"(r[8]), "l"(q) : "memory");
}

__device__ __forceinline__ void store_row_if(bool pred, char* p, char* q, const uint32_t (&r)[9]) {
    asm volatile("{ .reg .pred p; setp.ne.u32 p, %5, 0; @p st.global.L1::no_allocate.v4.u32 [%4], {%0,%1,%2,%3}; }"
                 :: "r"(r[0]), "r"(r[1]), "r"(r[2]), "r"(r[3]), "l"(p), "r"((uint32_t)pred) : "memory");
    asm volatile("{ .reg .pred p; setp.ne.u32 p, %5, 0; @p st.global.L1::no_allocate.v4.u32 [%4+512], {%0,%1,%2,%3}; }"
                 :: "r"(r[4]), "r"(r[5]), "r"(r[6]), "r"(r[7]), "l"(p), "r"((uint32_t)pred) : "memory");
    asm volatile("{ .reg .pred p; setp.ne.u32 p, %2, 0; @p st.global.L1::no_allocate.u32 [%1], %0; }"
                 :: "r"(r[8]), "l"(q), "r"((uint32_t)pred) : "memory");
}

__device__ __forceinline__ void normalize_row(uint32_t (&o)[9], const uint32_t (&y)[9],
                                              const uint32_t (&gv)[9], const uint32_t (&bv)[9]) {
    const float c = bf_lo(y[0]);
    float d[18];
    d[0] = 0.f;
    d[1] = bf_hi(y[0]) - c;
#pragma unroll
    for (int i = 1; i < 9; i++) { d[2 * i] = bf_lo(y[i]) - c; d[2 * i + 1] = bf_hi(y[i]) - c; }
    float s0 = d[3], s1 = d[1] + d[4], s2 = d[2] + d[5];
    float q0 = d[3] * d[3], q1 = fmaf(d[4], d[4], d[1] * d[1]), q2 = fmaf(d[5], d[5], d[2] * d[2]);
#pragma unroll
    for (int i = 6; i < 18; i += 3) {
        s0 += d[i]; s1 += d[i + 1]; s2 += d[i + 2];
        q0 = fmaf(d[i], d[i], q0); q1 = fmaf(d[i + 1], d[i + 1], q1); q2 = fmaf(d[i + 2], d[i + 2], q2);
    }
    const float s = (s0 + s1) + s2;
    const float mu = s * (1.0f / 18.0f);
    float q = fmaf(-s, mu, (q0 + q1) + q2);
    float m = c + mu;
    float half_n = 9.0f;
#pragma unroll
    for (int k = 1; k < 32; k <<= 1) {
        const float mo = __shfl_xor_sync(0xffffffffu, m, k);
        const float qo = __shfl_xor_sync(0xffffffffu, q, k);
        const float dm = mo - m;
        q = fmaf(dm * half_n, dm, q + qo);
        m = 0.5f * (m + mo);
        half_n *= 2.0f;
    }
    float rstd;
    asm("rsqrt.approx.ftz.f32 %0, %1;" : "=f"(rstd) : "f"(fmaf(q, 1.0f / kD, 1e-5f)));
    const float sh = (c - m) * rstd;
#pragma unroll
    for (int i = 0; i < 9; i++)
        o[i] = fma_bf2(pack_bf2(fmaf(d[2 * i], rstd, sh), fmaf(d[2 * i + 1], rstd, sh)), gv[i], bv[i]);
}

template <int ROUNDS>
__global__ void __launch_bounds__(kWarps * 32, 1)
deepnorm_paced_kernel(const char* __restrict__ x, const char* __restrict__ f, const char* __restrict__ g,
                      const char* __restrict__ b, const unsigned short* __restrict__ alpha_p,
                      char* __restrict__ out) {
    const uint32_t lane = threadIdx.x & 31;
    const uint32_t warp = threadIdx.x >> 5;
    const uint32_t c0 = now_clk();
    if (warp >= DN_W0) {
        const int del = (int)(warp - DN_W0 + 1) * DN_D0;
        while ((int)(now_clk() - c0) < del) {}
    }
    uint32_t araw;
    asm volatile("ld.global.nc.u16 %0, [%1];" : "=r"(araw) : "l"(alpha_p));
    uint32_t off = (blockIdx.x * kWarps + warp) * kRowBytes + lane * 16;
    const int tail = 1024 - (int)lane * 12;
    uint32_t gv[9], bv[9], xv[9], fv[9], held[9], o[9];
    load_param_row(gv, g + lane * 16, g + lane * 4 + 1024);
    load_param_row(bv, b + lane * 16, b + lane * 4 + 1024);
    load_row(xv, x + off, x + (off + tail));
    load_row(fv, f + off, f + (off + tail));
    const uint32_t ns_rel = now_ns() + (DN_TREL - (int)(now_clk() - c0)) / 2 + 200;
    const uint32_t a2 = araw * 0x10001u;
    uint32_t tnext = c0 + (kWarps - DN_W0) * DN_D0 + (warp + 1) * DN_D1;
    const bool holder = warp >= DN_HW;
#pragma unroll
    for (int i = 0; i < 9; i++) held[i] = 0;

#pragma unroll 1
    while (true) {
        uint32_t y[9];
#pragma unroll
        for (int i = 0; i < 9; i++) y[i] = fma_bf2(a2, xv[i], fv[i]);
        const uint32_t noff = off + kStride;
        const bool more = noff < ROUNDS * kStride;
        const bool now = (int)(now_clk() - tnext) >= 0;
        if (more && now) {
            load_row(xv, x + noff, x + (noff + tail));
            load_row(fv, f + noff, f + (noff + tail));
        }
        normalize_row(o, y, gv, bv);
        if (!more) {
            while ((int)(now_clk() - c0) < DN_TREL && (int)(now_ns() - ns_rel) < 0) {}
        }
        char* op = out + off;
        char* oq = out + (off + tail);
        const bool park = holder && noff + kStride >= ROUNDS * kStride;
        store_row_if(park && !more, op - kStride, oq - kStride, held);
        store_row_if(!(park && more), op, oq, o);
        if (!more) break;
#pragma unroll
        for (int i = 0; i < 9; i++) held[i] = o[i];
        if (!now) {
            while ((int)(now_clk() - tnext) < 0) {}
            load_row(xv, x + noff, x + (noff + tail));
            load_row(fv, f + noff, f + (noff + tail));
        }
        tnext += kWarps * DN_D1;
        off = noff;
    }
}

__global__ void __launch_bounds__(kWarps * 32)
deepnorm_generic_kernel(const char* __restrict__ x, const char* __restrict__ f, const char* __restrict__ g,
                        const char* __restrict__ b, const unsigned short* __restrict__ alpha_p,
                        char* __restrict__ out, uint32_t rows) {
    const uint32_t lane = threadIdx.x & 31;
    uint32_t gv[9], bv[9], xv[9], fv[9], y[9], o[9];
    const uint32_t a2 = (uint32_t)alpha_p[0] * 0x10001u;
    load_param_row(gv, g + lane * 16, g + lane * 4 + 1024);
    load_param_row(bv, b + lane * 16, b + lane * 4 + 1024);
    for (uint32_t row = blockIdx.x * kWarps + (threadIdx.x >> 5); row < rows; row += gridDim.x * kWarps) {
        const size_t base = (size_t)row * kRowBytes;
        load_row(xv, x + base + lane * 16, x + base + 1024 + lane * 4);
        load_row(fv, f + base + lane * 16, f + base + 1024 + lane * 4);
#pragma unroll
        for (int i = 0; i < 9; i++) y[i] = fma_bf2(a2, xv[i], fv[i]);
        normalize_row(o, y, gv, bv);
        store_row(out + base + lane * 16, out + base + 1024 + lane * 4, o);
    }
}

}

extern "C" void kernel_launch(void* const* d_in, const int* in_sizes, int n_in,
                              void* d_out, int out_size) {
    (void)n_in; (void)out_size;
    const char* x = (const char*)d_in[0];
    const char* f = (const char*)d_in[1];
    const char* g = (const char*)d_in[2];
    const char* b = (const char*)d_in[3];
    const unsigned short* alpha = (const unsigned short*)d_in[4];
    const uint32_t rows = (uint32_t)(in_sizes[0] / kD);
    int dev = 0, sms = 0;
    cudaGetDevice(&dev);
    cudaDeviceGetAttribute(&sms, cudaDevAttrMultiProcessorCount, dev);
    if (rows == 4 * kWarps * kGrid && sms >= kGrid) {
        deepnorm_paced_kernel<4><<<kGrid, kWarps * 32>>>(x, f, g, b, alpha, (char*)d_out);
    } else if (rows > 0) {
        uint32_t blocks = (rows + kWarps - 1) / kWarps;
        const uint32_t cap = (uint32_t)(sms > 0 ? sms : 1) * 2;
        if (blocks > cap) blocks = cap;
        deepnorm_generic_kernel<<<blocks, kWarps * 32>>>(x, f, g, b, alpha, (char*)d_out, rows);
    }
}
```

```cpp
#include <cuda_runtime.h>
#include <cuda_bf16.h>
#include <stdint.h>

namespace {

constexpr int kD = 576;
constexpr uint32_t kRowBytes = kD * 2;
constexpr int kWarps = 16;
constexpr int kGrid = 128;
constexpr int kRounds = 4;
constexpr uint32_t kStride = kWarps * kGrid * kRowBytes;

constexpr int kEarlyWarps = 3;
constexpr int kFirstGap = 170;
constexpr int kGap = 180;
constexpr int kRelease = 11900;
constexpr int kHoldFromWarp = 4;

__device__ __forceinline__ float bf_lo(uint32_t u) { return __uint_as_float(u << 16); }
__device__ __forceinline__ float bf_hi(uint32_t u) { return __uint_as_float(u & 0xffff0000u); }
__device__ __forceinline__ uint32_t pack_bf2(float lo, float hi) {
    uint32_t r;
    asm("cvt.rn.bf16x2.f32 %0, %1, %2;" : "=r"(r) : "f"(hi), "f"(lo));
    return r;
}
__device__ __forceinline__ uint32_t fma_bf2(uint32_t a, uint32_t b, uint32_t c) {
    uint32_t r;
    asm("fma.rn.bf16x2 %0, %1, %2, %3;" : "=r"(r) : "r"(a), "r"(b), "r"(c));
    return r;
}
__device__ __forceinline__ uint32_t now_clk() { return (uint32_t)clock(); }
__device__ __forceinline__ uint32_t now_ns() {
    uint32_t t;
    asm volatile("mov.u32 %0, %globaltimer_lo;" : "=r"(t));
    return t;
}

__device__ __forceinline__ void load_param_row(uint32_t (&r)[9], const char* p, const char* q) {
    asm volatile("ld.global.nc.v4.u32 {%0,%1,%2,%3}, [%4];"
                 : "=r"(r[0]), "=r"(r[1]), "=r"(r[2]), "=r"(r[3]) : "l"(p));
    asm volatile("ld.global.nc.v4.u32 {%0,%1,%2,%3}, [%4+512];"
                 : "=r"(r[4]), "=r"(r[5]), "=r"(r[6]), "=r"(r[7]) : "l"(p));
    asm volatile("ld.global.nc.u32 %0, [%1];" : "=r"(r[8]) : "l"(q));
}
__device__ __forceinline__ void load_row(uint32_t (&r)[9], const char* p, const char* q) {
    asm volatile("ld.global.nc.L1::no_allocate.v4.u32 {%0,%1,%2,%3}, [%4];"
                 : "=r"(r[0]), "=r"(r[1]), "=r"(r[2]), "=r"(r[3]) : "l"(p));
    asm volatile("ld.global.nc.L1::no_allocate.v4.u32 {%0,%1,%2,%3}, [%4+512];"
                 : "=r"(r[4]), "=r"(r[5]), "=r"(r[6]), "=r"(r[7]) : "l"(p));
    asm volatile("ld.global.nc.L1::no_allocate.u32 %0, [%1];" : "=r"(r[8]) : "l"(q));
}
__device__ __forceinline__ void store_row_if(bool pred, char* p, char* q, const uint32_t (&r)[9]) {
    asm volatile("{ .reg .pred p; setp.ne.u32 p, %5, 0;"
                 " @p st.global.L1::no_allocate.v4.u32 [%4], {%0,%1,%2,%3}; }"
                 :: "r"(r[0]), "r"(r[1]), "r"(r[2]), "r"(r[3]), "l"(p), "r"((uint32_t)pred) : "memory");
    asm volatile("{ .reg .pred p; setp.ne.u32 p, %5, 0;"
                 " @p st.global.L1::no_allocate.v4.u32 [%4+512], {%0,%1,%2,%3}; }"
                 :: "r"(r[4]), "r"(r[5]), "r"(r[6]), "r"(r[7]), "l"(p), "r"((uint32_t)pred) : "memory");
    asm volatile("{ .reg .pred p; setp.ne.u32 p, %2, 0; @p st.global.L1::no_allocate.u32 [%1], %0; }"
                 :: "r"(r[8]), "l"(q), "r"((uint32_t)pred) : "memory");
}

__device__ __forceinline__ void normalize_row(uint32_t (&o)[9], const uint32_t (&y)[9],
                                              const uint32_t (&gv)[9], const uint32_t (&bv)[9]) {
    const float c = bf_lo(y[0]);
    float d[18];
    d[0] = 0.f;
    d[1] = bf_hi(y[0]) - c;
#pragma unroll
    for (int i = 1; i < 9; i++) { d[2 * i] = bf_lo(y[i]) - c; d[2 * i + 1] = bf_hi(y[i]) - c; }
    float s0 = d[3], s1 = d[1] + d[4], s2 = d[2] + d[5];
    float q0 = d[3] * d[3], q1 = fmaf(d[4], d[4], d[1] * d[1]), q2 = fmaf(d[5], d[5], d[2] * d[2]);
#pragma unroll
    for (int i = 6; i < 18; i += 3) {
        s0 += d[i]; s1 += d[i + 1]; s2 += d[i + 2];
        q0 = fmaf(d[i], d[i], q0); q1 = fmaf(d[i + 1], d[i + 1], q1); q2 = fmaf(d[i + 2], d[i + 2], q2);
    }
    const float s = (s0 + s1) + s2;
    const float mu = s * (1.0f / 18.0f);
    float q = fmaf(-s, mu, (q0 + q1) + q2);
    float m = c + mu;
    float half_n = 9.0f;
#pragma unroll
    for (int k = 1; k < 32; k <<= 1) {
        const float mo = __shfl_xor_sync(0xffffffffu, m, k);
        const float qo = __shfl_xor_sync(0xffffffffu, q, k);
        const float dm = mo - m;
        q = fmaf(dm * half_n, dm, q + qo);
        m = 0.5f * (m + mo);
        half_n *= 2.0f;
    }
    float rstd;
    asm("rsqrt.approx.ftz.f32 %0, %1;" : "=f"(rstd) : "f"(fmaf(q, 1.0f / kD, 1e-5f)));
    const float sh = (c - m) * rstd;
#pragma unroll
    for (int i = 0; i < 9; i++)
        o[i] = fma_bf2(pack_bf2(fmaf(d[2 * i], rstd, sh), fmaf(d[2 * i + 1], rstd, sh)), gv[i], bv[i]);
}

__global__ void __launch_bounds__(kWarps * 32, 1)
deepnorm_paced_kernel(const char* __restrict__ x, const char* __restrict__ f, const char* __restrict__ g,
                      const char* __restrict__ b, const unsigned short* __restrict__ alpha_p,
                      char* __restrict__ out) {
    const uint32_t lane = threadIdx.x & 31;
    const uint32_t warp = threadIdx.x >> 5;
    const uint32_t c0 = now_clk();
    if (warp >= kEarlyWarps) {
        const int del = (int)(warp - kEarlyWarps + 1) * kFirstGap;
        while ((int)(now_clk() - c0) < del) {}
    }
    uint32_t araw;
    asm volatile("ld.global.nc.u16 %0, [%1];" : "=r"(araw) : "l"(alpha_p));
    uint32_t off = (blockIdx.x * kWarps + warp) * kRowBytes + lane * 16;
    const int tail = 1024 - (int)lane * 12;
    uint32_t gv[9], bv[9], xv[9], fv[9], held[9], o[9];
    load_param_row(gv, g + lane * 16, g + lane * 4 + 1024);
    load_param_row(bv, b + lane * 16, b + lane * 4 + 1024);
    load_row(xv, x + off, x + (off + tail));
    load_row(fv, f + off, f + (off + tail));
    const uint32_t ns_rel = now_ns() + (kRelease - (int)(now_clk() - c0)) / 2 + 200;
    const uint32_t a2 = araw * 0x10001u;
    uint32_t tnext = c0 + (kWarps - kEarlyWarps) * kFirstGap + (warp + 1) * kGap;
    const bool holder = warp >= kHoldFromWarp;
#pragma unroll
    for (int i = 0; i < 9; i++) held[i] = 0;

#pragma unroll 1
    while (true) {
        uint32_t y[9];
#pragma unroll
        for (int i = 0; i < 9; i++) y[i] = fma_bf2(a2, xv[i], fv[i]);
        const uint32_t noff = off + kStride;
        const bool more = noff < kRounds * kStride;
        const bool due = (int)(now_clk() - tnext) >= 0;
        if (more && due) {
            load_row(xv, x + noff, x + (noff + tail));
            load_row(fv, f + noff, f + (noff + tail));
        }
        normalize_row(o, y, gv, bv);
        if (!more) {
            while ((int)(now_clk() - c0) < kRelease && (int)(now_ns() - ns_rel) < 0) {}
        }
        char* op = out + off;
        char* oq = out + (off + tail);
        const bool park = holder && noff + kStride >= kRounds * kStride;
        store_row_if(park && !more, op - kStride, oq - kStride, held);
        store_row_if(!(park && more), op, oq, o);
        if (!more) break;
#pragma unroll
        for (int i = 0; i < 9; i++) held[i] = o[i];
        if (!due) {
            while ((int)(now_clk() - tnext) < 0) {}
            load_row(xv, x + noff, x + (noff + tail));
            load_row(fv, f + noff, f + (noff + tail));
        }
        tnext += kWarps * kGap;
        off = noff;
    }
}

__global__ void __launch_bounds__(kWarps * 32)
deepnorm_generic_kernel(const char* __restrict__ x, const char* __restrict__ f, const char* __restrict__ g,
                        const char* __restrict__ b, const unsigned short* __restrict__ alpha_p,
                        char* __restrict__ out, uint32_t rows) {
    const uint32_t lane = threadIdx.x & 31;
    uint32_t gv[9], bv[9], xv[9], fv[9], y[9], o[9];
    const uint32_t a2 = (uint32_t)alpha_p[0] * 0x10001u;
    load_param_row(gv, g + lane * 16, g + lane * 4 + 1024);
    load_param_row(bv, b + lane * 16, b + lane * 4 + 1024);
    for (uint32_t row = blockIdx.x * kWarps + (threadIdx.x >> 5); row < rows; row += gridDim.x * kWarps) {
        const size_t base = (size_t)row * kRowBytes;
        load_row(xv, x + base + lane * 16, x + base + 1024 + lane * 4);
        load_row(fv, f + base + lane * 16, f + base + 1024 + lane * 4);
#pragma unroll
        for (int i = 0; i < 9; i++) y[i] = fma_bf2(a2, xv[i], fv[i]);
        normalize_row(o, y, gv, bv);
        store_row_if(true, out + base + lane * 16, out + base + 1024 + lane * 4, o);
    }
}

}

extern "C" void kernel_launch(void* const* d_in, const int* in_sizes, int n_in,
                              void* d_out, int out_size) {
    (void)n_in; (void)out_size;
    const char* x = (const char*)d_in[0];
    const char* f = (const char*)d_in[1];
    const char* g = (const char*)d_in[2];
    const char* b = (const char*)d_in[3];
    const unsigned short* alpha = (const unsigned short*)d_in[4];
    const uint32_t rows = (uint32_t)(in_sizes[0] / kD);
    int dev = 0, sms = 0;
    cudaGetDevice(&dev);
    cudaDeviceGetAttribute(&sms, cudaDevAttrMultiProcessorCount, dev);
    if (rows == kRounds * kWarps * kGrid && sms >= kGrid) {
        deepnorm_paced_kernel<<<kGrid, kWarps * 32>>>(x, f, g, b, alpha, (char*)d_out);
    } else if (rows > 0) {
        uint32_t blocks = (rows + kWarps - 1) / kWarps;
        const uint32_t cap = (uint32_t)(sms > 0 ? sms : 1) * 2;
        if (blocks > cap) blocks = cap;
        deepnorm_generic_kernel<<<blocks, kWarps * 32>>>(x, f, g, b, alpha, (char*)d_out, rows);
    }
}
```

```cpp
#include <cuda_runtime.h>
#include <cuda_bf16.h>
#include <stdint.h>

namespace {

constexpr int kD = 576;
constexpr uint32_t kRowBytes = kD * 2;
constexpr int kWarps = 16;
constexpr int kGrid = 128;
constexpr int kRounds = 4;
constexpr uint32_t kStride = kWarps * kGrid * kRowBytes;

constexpr int kEarlyWarps = 3;
constexpr int kFirstGap = 170;
constexpr int kGap = 180;
constexpr int kRelease = 11820;
constexpr int kHoldFromWarp = 4;

__device__ __forceinline__ float bf_lo(uint32_t u) { return __uint_as_float(u << 16); }
__device__ __forceinline__ float bf_hi(uint32_t u) { return __uint_as_float(u & 0xffff0000u); }
__device__ __forceinline__ uint32_t pack_bf2(float lo, float hi) {
    uint32_t r;
    asm("cvt.rn.bf16x2.f32 %0, %1, %2;" : "=r"(r) : "f"(hi), "f"(lo));
    return r;
}
__device__ __forceinline__ uint32_t fma_bf2(uint32_t a, uint32_t b, uint32_t c) {
    uint32_t r;
    asm("fma.rn.bf16x2 %0, %1, %2, %3;" : "=r"(r) : "r"(a), "r"(b), "r"(c));
    return r;
}
__device__ __forceinline__ uint32_t scale_add_bf2(uint32_t a, uint32_t x, uint32_t f) {
    uint32_t r;
    asm("{ .reg .b32 t; mul.rn.bf16x2 t, %1, %2; add.rn.bf16x2 %0, t, %3; }" : "=r"(r) : "r"(a), "r"(x), "r"(f));
    return r;
}
__device__ __forceinline__ uint32_t now_clk() { return (uint32_t)clock(); }
__device__ __forceinline__ uint32_t now_ns() {
    uint32_t t;
    asm volatile("mov.u32 %0, %globaltimer_lo;" : "=r"(t));
    return t;
}

__device__ __forceinline__ void load_param_row(uint32_t (&r)[9], const char* p, const char* q) {
    asm volatile("ld.global.nc.v4.u32 {%0,%1,%2,%3}, [%4];"
                 : "=r"(r[0]), "=r"(r[1]), "=r"(r[2]), "=r"(r[3]) : "l"(p));
    asm volatile("ld.global.nc.v4.u32 {%0,%1,%2,%3}, [%4+512];"
                 : "=r"(r[4]), "=r"(r[5]), "=r"(r[6]), "=r"(r[7]) : "l"(p));
    asm volatile("ld.global.nc.u32 %0, [%1];" : "=r"(r[8]) : "l"(q));
}
__device__ __forceinline__ void load_row(uint32_t (&r)[9], const char* p, const char* q) {
    asm volatile("ld.global.nc.L1::no_allocate.v4.u32 {%0,%1,%2,%3}, [%4];"
                 : "=r"(r[0]), "=r"(r[1]), "=r"(r[2]), "=r"(r[3]) : "l"(p));
    asm volatile("ld.global.nc.L1::no_allocate.v4.u32 {%0,%1,%2,%3}, [%4+512];"
                 : "=r"(r[4]), "=r"(r[5]), "=r"(r[6]), "=r"(r[7]) : "l"(p));
    asm volatile("ld.global.nc.L1::no_allocate.u32 %0, [%1];" : "=r"(r[8]) : "l"(q));
}
__device__ __forceinline__ void load_row_ordered(uint32_t (&r)[9], const char* p, const char* q) {
    asm volatile("ld.relaxed.cta.global.L1::no_allocate.v4.u32 {%0,%1,%2,%3}, [%4];"
                 : "=r"(r[0]), "=r"(r[1]), "=r"(r[2]), "=r"(r[3]) : "l"(p) : "memory");
    asm volatile("ld.relaxed.cta.global.L1::no_allocate.v4.u32 {%0,%1,%2,%3}, [%4+512];"
                 : "=r"(r[4]), "=r"(r[5]), "=r"(r[6]), "=r"(r[7]) : "l"(p) : "memory");
    asm volatile("ld.relaxed.cta.global.L1::no_allocate.u32 %0, [%1];" : "=r"(r[8]) : "l"(q) : "memory");
}
__device__ __forceinline__ void load_param_row_ordered(uint32_t (&r)[9], const char* p, const char* q) {
    asm volatile("ld.relaxed.cta.global.v4.u32 {%0,%1,%2,%3}, [%4];"
                 : "=r"(r[0]), "=r"(r[1]), "=r"(r[2]), "=r"(r[3]) : "l"(p) : "memory");
    asm volatile("ld.relaxed.cta.global.v4.u32 {%0,%1,%2,%3}, [%4+512];"
                 : "=r"(r[4]), "=r"(r[5]), "=r"(r[6]), "=r"(r[7]) : "l"(p) : "memory");
    asm volatile("ld.relaxed.cta.global.u32 %0, [%1];" : "=r"(r[8]) : "l"(q) : "memory");
}
__device__ __forceinline__ void store_row_if(bool pred, char* p, char* q, const uint32_t (&r)[9]) {
    asm volatile("{ .reg .pred p; setp.ne.u32 p, %5, 0;"
                 " @p st.global.L1::no_allocate.v4.u32 [%4], {%0,%1,%2,%3}; }"
                 :: "r"(r[0]), "r"(r[1]), "r"(r[2]), "r"(r[3]), "l"(p), "r"((uint32_t)pred) : "memory");
    asm volatile("{ .reg .pred p; setp.ne.u32 p, %5, 0;"
                 " @p st.global.L1::no_allocate.v4.u32 [%4+512], {%0,%1,%2,%3}; }"
                 :: "r"(r[4]), "r"(r[5]), "r"(r[6]), "r"(r[7]), "l"(p), "r"((uint32_t)pred) : "memory");
    asm volatile("{ .reg .pred p; setp.ne.u32 p, %2, 0; @p st.global.L1::no_allocate.u32 [%1], %0; }"
                 :: "r"(r[8]), "l"(q), "r"((uint32_t)pred) : "memory");
}

__device__ __forceinline__ void normalize_row(uint32_t (&o)[9], const uint32_t (&y)[9],
                                              const uint32_t (&gv)[9], const uint32_t (&bv)[9]) {
    const float c = bf_lo(y[0]);
    float d[18];
    d[0] = 0.f;
    d[1] = bf_hi(y[0]) - c;
#pragma unroll
    for (int i = 1; i < 9; i++) { d[2 * i] = bf_lo(y[i]) - c; d[2 * i + 1] = bf_hi(y[i]) - c; }
    float s0 = d[3], s1 = d[1] + d[4], s2 = d[2] + d[5];
    float q0 = d[3] * d[3], q1 = fmaf(d[4], d[4], d[1] * d[1]), q2 = fmaf(d[5], d[5], d[2] * d[2]);
#pragma unroll
    for (int i = 6; i < 18; i += 3) {
        s0 += d[i]; s1 += d[i + 1]; s2 += d[i + 2];
        q0 = fmaf(d[i], d[i], q0); q1 = fmaf(d[i + 1], d[i + 1], q1); q2 = fmaf(d[i + 2], d[i + 2], q2);
    }
    const float s = (s0 + s1) + s2;
    const float mu = s * (1.0f / 18.0f);
    float q = fmaf(-s, mu, (q0 + q1) + q2);
    float m = c + mu;
    float half_n = 9.0f;
#pragma unroll
    for (int k = 1; k < 32; k <<= 1) {
        const float mo = __shfl_xor_sync(0xffffffffu, m, k);
        const float qo = __shfl_xor_sync(0xffffffffu, q, k);
        const float dm = mo - m;
        q = fmaf(dm * half_n, dm, q + qo);
        m = 0.5f * (m + mo);
        half_n *= 2.0f;
    }
    float rstd;
    asm("rsqrt.approx.ftz.f32 %0, %1;" : "=f"(rstd) : "f"(fmaf(q, 1.0f / kD, 1e-5f)));
    const float sh = (c - m) * rstd;
#pragma unroll
    for (int i = 0; i < 9; i++)
        o[i] = fma_bf2(pack_bf2(fmaf(d[2 * i], rstd, sh), fmaf(d[2 * i + 1], rstd, sh)), gv[i], bv[i]);
}

__global__ void __launch_bounds__(kWarps * 32, 1)
deepnorm_paced_kernel(const char* __restrict__ x, const char* __restrict__ f, const char* __restrict__ g,
                      const char* __restrict__ b, const unsigned short* __restrict__ alpha_p,
                      char* __restrict__ out) {
    const uint32_t lane = threadIdx.x & 31;
    const uint32_t warp = threadIdx.x >> 5;
    const uint32_t c0 = now_clk();
    uint32_t off = (blockIdx.x * kWarps + warp) * kRowBytes + lane * 16;
    const int tail = 1024 - (int)lane * 12;
    uint32_t gv[9], bv[9], xv[9], fv[9], held[9], o[9], araw;
    if (warp >= kEarlyWarps) {
        const int del = (int)(warp - kEarlyWarps + 1) * kFirstGap;
        while ((int)(now_clk() - c0) < del) {}
    }
    load_row_ordered(xv, x + off, x + (off + tail));
    load_row_ordered(fv, f + off, f + (off + tail));
    asm volatile("ld.relaxed.cta.global.u16 %0, [%1];" : "=r"(araw) : "l"(alpha_p) : "memory");
    load_param_row_ordered(gv, g + lane * 16, g + lane * 4 + 1024);
    load_param_row_ordered(bv, b + lane * 16, b + lane * 4 + 1024);
    const uint32_t ns_rel = now_ns() + (kRelease - (int)(now_clk() - c0)) / 2 + 200;
    const uint32_t a2 = araw * 0x10001u;
    uint32_t tnext = c0 + (kWarps - kEarlyWarps) * kFirstGap + (warp + 1) * kGap;
    const bool holder = warp >= kHoldFromWarp;
#pragma unroll
    for (int i = 0; i < 9; i++) held[i] = 0;

#pragma unroll 1
    while (true) {
        uint32_t y[9];
#pragma unroll
        for (int i = 0; i < 9; i++) y[i] = scale_add_bf2(a2, xv[i], fv[i]);
        const uint32_t noff = off + kStride;
        const bool more = noff < kRounds * kStride;
        const bool due = (int)(now_clk() - tnext) >= 0;
        if (more && due) {
            load_row(xv, x + noff, x + (noff + tail));
            load_row(fv, f + noff, f + (noff + tail));
        }
        normalize_row(o, y, gv, bv);
        if (!more) {
            while ((int)(now_clk() - c0) < kRelease && (int)(now_ns() - ns_rel) < 0) {}
        }
        char* op = out + off;
        char* oq = out + (off + tail);
        const bool park = holder && noff + kStride >= kRounds * kStride;
        store_row_if(park && !more, op - kStride, oq - kStride, held);
        store_row_if(!(park && more), op, oq, o);
        if (!more) break;
#pragma unroll
        for (int i = 0; i < 9; i++) held[i] = o[i];
        if (!due) {
            while ((int)(now_clk() - tnext) < 0) {}
            load_row(xv, x + noff, x + (noff + tail));
            load_row(fv, f + noff, f + (noff + tail));
        }
        tnext += kWarps * kGap;
        off = noff;
    }
}

__global__ void __launch_bounds__(kWarps * 32)
deepnorm_generic_kernel(const char* __restrict__ x, const char* __restrict__ f, const char* __restrict__ g,
                        const char* __restrict__ b, const unsigned short* __restrict__ alpha_p,
                        char* __restrict__ out, uint32_t rows) {
    const uint32_t lane = threadIdx.x & 31;
    uint32_t gv[9], bv[9], xv[9], fv[9], y[9], o[9];
    const uint32_t a2 = (uint32_t)alpha_p[0] * 0x10001u;
    load_param_row(gv, g + lane * 16, g + lane * 4 + 1024);
    load_param_row(bv, b + lane * 16, b + lane * 4 + 1024);
    for (uint32_t row = blockIdx.x * kWarps + (threadIdx.x >> 5); row < rows; row += gridDim.x * kWarps) {
        const size_t base = (size_t)row * kRowBytes;
        load_row(xv, x + base + lane * 16, x + base + 1024 + lane * 4);
        load_row(fv, f + base + lane * 16, f + base + 1024 + lane * 4);
#pragma unroll
        for (int i = 0; i < 9; i++) y[i] = scale_add_bf2(a2, xv[i], fv[i]);
        normalize_row(o, y, gv, bv);
        store_row_if(true, out + base + lane * 16, out + base + 1024 + lane * 4, o);
    }
}

}

extern "C" void kernel_launch(void* const* d_in, const int* in_sizes, int n_in,
                              void* d_out, int out_size) {
    (void)n_in; (void)out_size;
    const char* x = (const char*)d_in[0];
    const char* f = (const char*)d_in[1];
    const char* g = (const char*)d_in[2];
    const char* b = (const char*)d_in[3];
    const unsigned short* alpha = (const unsigned short*)d_in[4];
    const uint32_t rows = (uint32_t)(in_sizes[0] / kD);
    int dev = 0, sms = 0;
    cudaGetDevice(&dev);
    cudaDeviceGetAttribute(&sms, cudaDevAttrMultiProcessorCount, dev);
    if (rows == kRounds * kWarps * kGrid && sms >= kGrid) {
        deepnorm_paced_kernel<<<kGrid, kWarps * 32>>>(x, f, g, b, alpha, (char*)d_out);
    } else if (rows > 0) {
        uint32_t blocks = (rows + kWarps - 1) / kWarps;
        const uint32_t cap = (uint32_t)(sms > 0 ? sms : 1) * 2;
        if (blocks > cap) blocks = cap;
        deepnorm_generic_kernel<<<blocks, kWarps * 32>>>(x, f, g, b, alpha, (char*)d_out, rows);
    }
}
```
